```python
import torch

def _softmax(x, axis=-1):
    return torch.softmax(x, dim=axis)
def _gelu(x):
    return torch.nn.functional.gelu(x, approximate="tanh")
def _silu(x):
    return torch.nn.functional.silu(x)
def _sigmoid(x):
    return torch.sigmoid(x)
def _layernorm(x, axis=-1, eps=1e-5):
    m = x.mean(dim=axis, keepdim=True)
    v = x.var(dim=axis, keepdim=True, unbiased=False)
    return (x - m) / torch.sqrt(v + eps)
def _scatter_add(tgt, idx, src, axis=0):
    return tgt.clone().index_add_(axis, idx, src)
def _segment_sum(src, seg, n):
    out = torch.zeros((n,) + src.shape[1:], dtype=src.dtype)
    return out.index_add_(0, seg, src)
def _pad(x, pw):
    flat = tuple(v for pair in reversed(pw) for v in pair)
    return torch.nn.functional.pad(x, flat)

kernel_name = 'gated_mix__ssm_conv_s5__dense_activation_gelu__prompt'

def setup_inputs():

    _w = (lambda a: (lambda t: t.to(torch.bfloat16) if t.is_floating_point() else t)(torch.as_tensor(a)))
    def _A_setup():
        B, S, D = 1, 2048, 512
        P = D
        Lambda_re = -0.5 * (lambda _x: torch.exp(torch.as_tensor(_x)))((lambda *s: torch.randn(*s, dtype=torch.bfloat16) * 0.2)(P))
        Lambda_im = (lambda *s: torch.randn(*s, dtype=torch.bfloat16) * 0.8)(P) * 1.0
        B_re = (lambda *s: torch.randn(*s, dtype=torch.bfloat16) * 0.2)(P, D) * (D ** -0.5)
        B_im = (lambda *s: torch.randn(*s, dtype=torch.bfloat16) * 0.2)(P, D) * (D ** -0.5)
        C_re = (lambda *s: torch.randn(*s, dtype=torch.bfloat16) * 0.2)(D, P) * (P ** -0.5)
        C_im = (lambda *s: torch.randn(*s, dtype=torch.bfloat16) * 0.2)(D, P) * (P ** -0.5)
        log_dt = (lambda *s: torch.randn(*s, dtype=torch.bfloat16) * 0.2)(P) * 0.3 - 2.0
        Dskip = (lambda *s: torch.randn(*s, dtype=torch.bfloat16) * 0.05)(D)
        return {
            "x": _w((lambda *s: torch.randn(*s, dtype=torch.bfloat16) * 0.05)(B, S, D)),
            "Lambda_re": _w(Lambda_re),
            "Lambda_im": _w(Lambda_im),
            "B_re": _w(B_re),
            "B_im": _w(B_im),
            "C_re": _w(C_re),
            "C_im": _w(C_im),
            "log_dt": _w(log_dt),
            "Dskip": _w(Dskip),
        }
    _A_in = _A_setup()

    def _B_setup():
        B, S, D, F = 1, 2048, 512, 1792
        return {
            "x": _w((lambda *s: torch.randn(*s, dtype=torch.bfloat16) * 0.05)(B, S, D)),
            "w1": _w((lambda *s: torch.randn(*s, dtype=torch.bfloat16) * 3.2)(D, F) * (D ** -0.5)),
            "b1": _w((lambda *s: torch.randn(*s, dtype=torch.bfloat16) * 3.2)(F) * 0.01),
            "w2": _w((lambda *s: torch.randn(*s, dtype=torch.bfloat16) * 0.1)(F, D) * (F ** -0.5)),
            "b2": _w((lambda *s: torch.randn(*s, dtype=torch.bfloat16) * 0.2)(D) * 0.01),
        }
    _B_in = _B_setup()

    return {
        "A_x": _A_in["x"],
        "A_Lambda_re": _A_in["Lambda_re"],
        "A_Lambda_im": _A_in["Lambda_im"],
        "A_B_re": _A_in["B_re"],
        "A_B_im": _A_in["B_im"],
        "A_C_re": _A_in["C_re"],
        "A_C_im": _A_in["C_im"],
        "A_log_dt": _A_in["log_dt"],
        "A_Dskip": _A_in["Dskip"],
        "B_x": _B_in["x"],
        "B_w1": _B_in["w1"],
        "B_b1": _B_in["b1"],
        "B_w2": _B_in["w2"],
        "B_b2": _B_in["b2"],
        "gate_w": _w((lambda *s: torch.randn(*s, dtype=torch.bfloat16) * 0.05)(512) * 16.0),
    }

def reference(A_x, A_Lambda_re, A_Lambda_im, A_B_re, A_B_im, A_C_re, A_C_im, A_log_dt, A_Dskip, B_x, B_w1, B_b1, B_w2, B_b2, gate_w):
    def _A_ref(x, Lambda_re, Lambda_im, B_re, B_im, C_re, C_im, log_dt, Dskip):
        Bsz, L, H = x.shape
        Lam = Lambda_re + 1j * Lambda_im
        Bmat = B_re + 1j * B_im
        Cmat = C_re + 1j * C_im
        dt = torch.exp(log_dt)
        Lam_bar = torch.exp(dt * Lam)
        B_bar = ((Lam_bar - 1.0) / Lam)[:, None] * Bmat
        Bu = torch.einsum("bld,pd->blp", x + 0j, B_bar)
        h = torch.zeros_like(Bu[:, 0, :])
        hs = []
        for t in range(L):
            h = Lam_bar[None, :] * h + Bu[:, t, :]
            hs.append(h)
        hseq = torch.stack(hs, 1)
        y = 2.0 * torch.einsum("blp,dp->bld", hseq, Cmat).real + x * Dskip[None, None, :]
        return y

    def _B_ref(x, w1, b1, w2, b2):
        h = torch.einsum("bsd,df->bsf", x, w1) + b1
        h = _gelu(h)
        return torch.einsum("bsf,fd->bsd", h, w2) + b2

    x = A_x
    g = _sigmoid((x * gate_w).sum(-1, keepdims=True))
    a = _A_ref(x, A_Lambda_re, A_Lambda_im, A_B_re, A_B_im, A_C_re, A_C_im, A_log_dt, A_Dskip)
    b = _B_ref(x, B_w1, B_b1, B_w2, B_b2)
    return g * a + (1 - g) * b
```

```cpp
#include <cuda_runtime.h>
#include <cuda_bf16.h>
#include <cuda.h>
#include <stdint.h>

namespace {

#define T_P1 8, 12, 11, 0, 0, 0, 0, 0, 0, 0, 0, 0, 0, 0, 0, 0
#define T_CF 0, 0, 0, 0, 8, 8, 8, 8, 0, 0, 0, 0, 0, 0, 0, 0
#define T_P2 0, 0, 0, 0, 0, 0, 0, 0, 0, 2, 2, 2, 2, 2, 4, 2
#define T_G1 0, 0, 0, 0, 0, 0, 0, 0, 1, 1, 1, 1, 1, 1, 0, 0
constexpr int XP_ST = 11;
constexpr int U1 = 6, U2 = 8;

constexpr int NTHREADS = 384;
constexpr uint32_t SBASE = 1024;
constexpr uint32_t SLOT = 16384;
constexpr uint32_t OFF_X = SBASE;
constexpr uint32_t OFF_R = OFF_X + 8 * SLOT;
constexpr int NRING = 5;
constexpr uint32_t OFF_BAR = OFF_R + NRING * SLOT;
constexpr uint32_t OFF_G = OFF_BAR + 1024;
constexpr uint32_t OFF_OMG = OFF_G + 256;
constexpr uint32_t OFF_PHI = OFF_OMG + 256;
constexpr uint32_t OFF_RHO = OFF_PHI + 256;
constexpr uint32_t OFF_B1 = OFF_RHO + 256;
constexpr uint32_t OFF_DS = OFF_B1 + 512;
constexpr uint32_t OFF_B2 = OFF_DS + 128;
constexpr uint32_t OFF_GW = OFF_B2 + 128;
constexpr uint32_t OFF_TAG = OFF_GW + 1024;
constexpr uint32_t OFF_PAR = OFF_TAG + 256;
constexpr uint32_t OFF_PW = OFF_PAR + 1024;
constexpr uint32_t OFF_F = OFF_PW + 1024;
constexpr uint32_t F_STRIDE = 72 * 8;
constexpr uint32_t SMEM_END = OFF_F + 4 * F_STRIDE;
constexpr int SMEM_BYTES = SMEM_END - SBASE;

constexpr int B_FULL = 0;
constexpr int B_FULLG = 24;
constexpr int B_EMPTY = 32;
constexpr int B_EMPTYG = 56;
constexpr int B_INI = 61, B_AS0 = 62, B_PEER = 63;
constexpr int B_FULL0S = 64, B_FULL1S = 65, B_FULL01B = 66, B_G = 67, B_PAR = 68, B_S = 69, B_F = 70, B_H = 71;
constexpr int B_D = 72;
__device__ __forceinline__ constexpr uint32_t bar(int i) { return OFF_BAR + 8u * i; }

struct Scratch {
  uint2 carry[16 * 512];
  uint32_t gate[16 * 128];
  uint4 part[16 * 8 * 2 * 1024];
};
__device__ Scratch g_scratch;

struct Params {
  const __nv_bfloat16 *dskip, *b1, *b2, *w1, *cre, *cim, *w2;
  CUtensorMap mx, mb, mw1a, mw1b, mc[2], mw2a, mw2b, mo;
};


constexpr int SPIN_LIMIT = 1 << 17;
constexpr int POLL_LIMIT = 1 << 21;

__device__ __forceinline__ void trap_if_ne(uint32_t a, uint32_t b) {
  asm volatile("{\n.reg .pred p;\nsetp.ne.u32 p, %0, %1;\n@p trap;\n}\n" ::"r"(a), "r"(b));
}
template <int K> __device__ __forceinline__ void sched_fence(uint32_t v) {
  asm volatile("{\n.reg .pred p;\nsetp.eq.u32 p, %0, %1;\n@p trap;\n}\n" ::"r"(v), "n"(2 * K + 1) : "memory");
}
__device__ __forceinline__ bool elect_one() {
  uint32_t r;
  asm volatile("{\n.reg .pred p;\nelect.sync _|p, 0xffffffff;\nselp.u32 %0, 1, 0, p;\n}\n" : "=r"(r));
  return r != 0;
}

__device__ __forceinline__ void mbar_init(uint32_t a, uint32_t c) {
  asm volatile("mbarrier.init.shared::cta.b64 [%0], %1;" ::"r"(a), "r"(c) : "memory");
}
__device__ __forceinline__ void mbar_expect(uint32_t a, uint32_t b) {
  asm volatile("mbarrier.arrive.expect_tx.shared::cta.b64 _, [%0], %1;" ::"r"(a), "r"(b) : "memory");
}
__device__ __forceinline__ void mbar_wait(uint32_t a) {
  asm volatile(
      "{\n.reg .pred p;\n.reg .u32 n;\n"
      "mbarrier.try_wait.parity.shared::cta.b64 p, [%0], 0;\n"
      "@p bra DONE;\n"
      "mov.u32 n, 0;\n"
      "LOOP:\n"
      "mbarrier.try_wait.parity.shared::cta.b64 p, [%0], 0, 20000;\n"
      "@p bra DONE;\n"
      "add.u32 n, n, 1;\n"
      "setp.lt.u32 p, n, %1;\n"
      "@p bra LOOP;\n"
      "trap;\n"
      "DONE:\n}\n" ::"r"(a), "n"(SPIN_LIMIT) : "memory");
}
__device__ __forceinline__ void warp_arrive(uint32_t a) {
  __syncwarp();
  if ((threadIdx.x & 31) == 0) asm volatile("mbarrier.arrive.shared::cta.b64 _, [%0];" ::"r"(a) : "memory");
}
__device__ __forceinline__ void lane_arrive(uint32_t base, uint32_t a) {
  asm volatile("{\n.reg .pred p;\nsetp.ge.s32 p, %0, 0;\n@p mbarrier.arrive.shared::cta.b64 _, [%1];\n}\n" ::"r"(base), "r"(base + a) : "memory");
}
__device__ __forceinline__ void lane_arrive_remote(uint32_t base, uint32_t a) {
  asm volatile("{\n.reg .pred p;\nsetp.ge.s32 p, %0, 0;\n@p mbarrier.arrive.shared::cluster.b64 _, [%1];\n}\n" ::"r"(base), "r"(base + a) : "memory");
}
__device__ __forceinline__ void st_peer(uint32_t a, uint32_t b, uint32_t x, uint32_t y, uint32_t z, uint32_t w) {
  asm volatile("st.async.weak.shared::cluster.mbarrier::complete_tx::bytes.v4.b32 [%0], {%2, %3, %4, %5}, [%1];"
               ::"r"(a), "r"(b), "r"(x), "r"(y), "r"(z), "r"(w) : "memory");
}
__device__ __forceinline__ void cluster_arrive() { asm volatile("barrier.cluster.arrive.relaxed.aligned;" ::: "memory"); }
__device__ __forceinline__ void cluster_wait() { asm volatile("barrier.cluster.wait.aligned;" ::: "memory"); }
__device__ __forceinline__ void nbar_sync(int id, int n) { asm volatile("bar.sync %0, %1;" ::"r"(id), "r"(n) : "memory"); }
__device__ __forceinline__ void nbar_arrive(int id, int n) { asm volatile("bar.arrive %0, %1;" ::"r"(id), "r"(n) : "memory"); }

__device__ __forceinline__ void tma2(uint32_t dst, const CUtensorMap* m, uint32_t b, int c0, int c1) {
  asm volatile("cp.async.bulk.tensor.2d.shared::cluster.global.mbarrier::complete_tx::bytes [%0], [%1, {%3, %4}], [%2];"
               ::"r"(dst), "l"(m), "r"(b), "r"(c0), "r"(c1) : "memory");
}
__device__ __forceinline__ void tma3(uint32_t dst, const CUtensorMap* m, uint32_t b, int c1, int c2) {
  asm volatile("cp.async.bulk.tensor.3d.shared::cluster.global.mbarrier::complete_tx::bytes [%0], [%1, {%5, %3, %4}], [%2];"
               ::"r"(dst), "l"(m), "r"(b), "r"(c1), "r"(c2), "r"(0) : "memory");
}
__device__ __forceinline__ void tma4(uint32_t dst, const CUtensorMap* m, uint32_t b, int c0, int c3) {
  asm volatile("cp.async.bulk.tensor.4d.shared::cluster.global.mbarrier::complete_tx::bytes [%0], [%1, {%3, %5, %5, %4}], [%2];"
               ::"r"(dst), "l"(m), "r"(b), "r"(c0), "r"(c3), "r"(0) : "memory");
}
template <bool MC>
__device__ __forceinline__ void tma5(uint32_t dst, const CUtensorMap* m, uint32_t b, int c0, int c3, int c4) {
  if (MC)
    asm volatile("cp.async.bulk.tensor.5d.shared::cluster.global.mbarrier::complete_tx::bytes.multicast::cluster [%0], [%1, {%3, %6, %6, %4, %5}], [%2], %7;"
                 ::"r"(dst), "l"(m), "r"(b), "r"(c0), "r"(c3), "r"(c4), "r"(0), "h"((uint16_t)3) : "memory");
  else
    asm volatile("cp.async.bulk.tensor.5d.shared::cluster.global.mbarrier::complete_tx::bytes [%0], [%1, {%3, %6, %6, %4, %5}], [%2];"
                 ::"r"(dst), "l"(m), "r"(b), "r"(c0), "r"(c3), "r"(c4), "r"(0) : "memory");
}
__device__ __forceinline__ void tma5_store(const CUtensorMap* m, uint32_t src, int c0, int c3, int c4) {
  asm volatile("cp.async.bulk.tensor.5d.global.shared::cta.bulk_group [%0, {%2, %5, %5, %3, %4}], [%1];"
               ::"l"(m), "r"(src), "r"(c0), "r"(c3), "r"(c4), "r"(0) : "memory");
}
__device__ __forceinline__ void prefetch_map(const CUtensorMap* m) { asm volatile("prefetch.tensormap [%0];" ::"l"(m) : "memory"); }
__device__ __forceinline__ void prefetch_l2(const void* p, uint32_t bytes) {
  asm volatile("cp.async.bulk.prefetch.L2.global [%0], %1;" ::"l"(p), "r"(bytes) : "memory");
}

__device__ __forceinline__ void wg_fence() { asm volatile("wgmma.fence.sync.aligned;" ::: "memory"); }
__device__ __forceinline__ void wg_commit() { asm volatile("wgmma.commit_group.sync.aligned;" ::: "memory"); }
template <int N> __device__ __forceinline__ void wg_wait() { asm volatile("wgmma.wait_group.sync.aligned %0;" ::"n"(N) : "memory"); }
template <int N> __device__ __forceinline__ void reg_fence(float (&d)[N]) {
#pragma unroll
  for (int i = 0; i < N; i++) asm volatile("" : "+f"(d[i])::"memory");
}
__device__ __forceinline__ uint64_t desc(uint32_t base16, uint32_t addr, uint32_t lbo, uint32_t sbo, uint32_t sw) {
  uint32_t lo = base16 + ((addr >> 4) | ((lbo >> 4) << 16));
  uint32_t hi = (sbo >> 4) | (sw << 30);
  return ((uint64_t)hi << 32) | lo;
}

template <int TA, int TB, int SA = 1>
__device__ __forceinline__ void wgmma_rs_n64(float (&d)[32], const uint32_t* a, uint64_t db, int scale_d) {
  asm volatile("{\n.reg .pred p;\nsetp.ne.b32 p, %37, 0;\n"
    "wgmma.mma_async.sync.aligned.m64n64k16.f32.bf16.bf16 "
    "{%0, %1, %2, %3, %4, %5, %6, %7, %8, %9, %10, %11, %12, %13, %14, %15, "
    "%16, %17, %18, %19, %20, %21, %22, %23, %24, %25, %26, %27, %28, %29, %30, %31}, "
    "{%32, %33, %34, %35}, %36, p, %39, 1, %38;\n}\n"
    : "+f"(d[0]), "+f"(d[1]), "+f"(d[2]), "+f"(d[3]), "+f"(d[4]), "+f"(d[5]), "+f"(d[6]), "+f"(d[7]),
      "+f"(d[8]), "+f"(d[9]), "+f"(d[10]), "+f"(d[11]), "+f"(d[12]), "+f"(d[13]), "+f"(d[14]), "+f"(d[15]),
      "+f"(d[16]), "+f"(d[17]), "+f"(d[18]), "+f"(d[19]), "+f"(d[20]), "+f"(d[21]), "+f"(d[22]), "+f"(d[23]),
      "+f"(d[24]), "+f"(d[25]), "+f"(d[26]), "+f"(d[27]), "+f"(d[28]), "+f"(d[29]), "+f"(d[30]), "+f"(d[31])
    : "r"(a[0]), "r"(a[1]), "r"(a[2]), "r"(a[3]), "l"(db), "r"(scale_d), "n"(TB), "n"(SA));
}
template <int TA, int TB, int SA = 1>
__device__ __forceinline__ void wgmma_ss_n128(float (&d)[64], uint64_t da, uint64_t db, int scale_d) {
  asm volatile("{\n.reg .pred p;\nsetp.ne.b32 p, %66, 0;\n"
    "wgmma.mma_async.sync.aligned.m64n128k16.f32.bf16.bf16 "
    "{%0, %1, %2, %3, %4, %5, %6, %7, %8, %9, %10, %11, %12, %13, %14, %15, "
    "%16, %17, %18, %19, %20, %21, %22, %23, %24, %25, %26, %27, %28, %29, %30, %31, "
    "%32, %33, %34, %35, %36, %37, %38, %39, %40, %41, %42, %43, %44, %45, %46, %47, "
    "%48, %49, %50, %51, %52, %53, %54, %55, %56, %57, %58, %59, %60, %61, %62, %63}, "
    "%64, %65, p, %69, 1, %67, %68;\n}\n"
    : "+f"(d[0]), "+f"(d[1]), "+f"(d[2]), "+f"(d[3]), "+f"(d[4]), "+f"(d[5]), "+f"(d[6]), "+f"(d[7]),
      "+f"(d[8]), "+f"(d[9]), "+f"(d[10]), "+f"(d[11]), "+f"(d[12]), "+f"(d[13]), "+f"(d[14]), "+f"(d[15]),
      "+f"(d[16]), "+f"(d[17]), "+f"(d[18]), "+f"(d[19]), "+f"(d[20]), "+f"(d[21]), "+f"(d[22]), "+f"(d[23]),
      "+f"(d[24]), "+f"(d[25]), "+f"(d[26]), "+f"(d[27]), "+f"(d[28]), "+f"(d[29]), "+f"(d[30]), "+f"(d[31]),
      "+f"(d[32]), "+f"(d[33]), "+f"(d[34]), "+f"(d[35]), "+f"(d[36]), "+f"(d[37]), "+f"(d[38]), "+f"(d[39]),
      "+f"(d[40]), "+f"(d[41]), "+f"(d[42]), "+f"(d[43]), "+f"(d[44]), "+f"(d[45]), "+f"(d[46]), "+f"(d[47]),
      "+f"(d[48]), "+f"(d[49]), "+f"(d[50]), "+f"(d[51]), "+f"(d[52]), "+f"(d[53]), "+f"(d[54]), "+f"(d[55]),
      "+f"(d[56]), "+f"(d[57]), "+f"(d[58]), "+f"(d[59]), "+f"(d[60]), "+f"(d[61]), "+f"(d[62]), "+f"(d[63])
    : "l"(da), "l"(db), "r"(scale_d), "n"(TA), "n"(TB), "n"(SA));
}
template <int TA, int TB, int SA = 1>
__device__ __forceinline__ void wgmma_ss_n96(float (&d)[48], uint64_t da, uint64_t db, int scale_d) {
  asm volatile("{\n.reg .pred p;\nsetp.ne.b32 p, %50, 0;\n"
    "wgmma.mma_async.sync.aligned.m64n96k16.f32.bf16.bf16 "
    "{%0, %1, %2, %3, %4, %5, %6, %7, %8, %9, %10, %11, %12, %13, %14, %15, "
    "%16, %17, %18, %19, %20, %21, %22, %23, %24, %25, %26, %27, %28, %29, %30, %31, "
    "%32, %33, %34, %35, %36, %37, %38, %39, %40, %41, %42, %43, %44, %45, %46, %47}, "
    "%48, %49, p, %53, 1, %51, %52;\n}\n"
    : "+f"(d[0]), "+f"(d[1]), "+f"(d[2]), "+f"(d[3]), "+f"(d[4]), "+f"(d[5]), "+f"(d[6]), "+f"(d[7]),
      "+f"(d[8]), "+f"(d[9]), "+f"(d[10]), "+f"(d[11]), "+f"(d[12]), "+f"(d[13]), "+f"(d[14]), "+f"(d[15]),
      "+f"(d[16]), "+f"(d[17]), "+f"(d[18]), "+f"(d[19]), "+f"(d[20]), "+f"(d[21]), "+f"(d[22]), "+f"(d[23]),
      "+f"(d[24]), "+f"(d[25]), "+f"(d[26]), "+f"(d[27]), "+f"(d[28]), "+f"(d[29]), "+f"(d[30]), "+f"(d[31]),
      "+f"(d[32]), "+f"(d[33]), "+f"(d[34]), "+f"(d[35]), "+f"(d[36]), "+f"(d[37]), "+f"(d[38]), "+f"(d[39]),
      "+f"(d[40]), "+f"(d[41]), "+f"(d[42]), "+f"(d[43]), "+f"(d[44]), "+f"(d[45]), "+f"(d[46]), "+f"(d[47])
    : "l"(da), "l"(db), "r"(scale_d), "n"(TA), "n"(TB), "n"(SA));
}

__device__ __forceinline__ void st_pkt(void* p, uint32_t a, uint32_t b, uint32_t c, uint32_t d) {
  asm volatile("st.relaxed.gpu.global.v4.b32 [%0], {%1, %2, %3, %4};" ::"l"(p), "r"(a), "r"(b), "r"(c), "r"(d) : "memory");
}
__device__ __forceinline__ void ld_pkt(const void* p, uint32_t* v) {
  asm volatile("ld.relaxed.gpu.global.v4.b32 {%0, %1, %2, %3}, [%4];" : "=r"(v[0]), "=r"(v[1]), "=r"(v[2]), "=r"(v[3]) : "l"(p) : "memory");
}
__device__ __forceinline__ void st_pkt8(void* p, uint32_t a, uint32_t b) {
  asm volatile("{\n.reg .b64 v;\nmov.b64 v, {%1, %2};\nst.relaxed.gpu.global.b64 [%0], v;\n}\n" ::"l"(p), "r"(a), "r"(b) : "memory");
}
__device__ __forceinline__ uint32_t ld_tag(const void* p) {
  uint32_t v; asm volatile("ld.relaxed.gpu.global.u32 %0, [%1];" : "=r"(v) : "l"(p) : "memory"); return (v & 1u) ^ 1u;
}
__device__ __forceinline__ uint32_t or_xor(uint32_t acc, uint32_t v, uint32_t tag) {
  asm("lop3.b32 %0, %0, %1, %2, 0xf6;" : "+r"(acc) : "r"(v), "r"(tag)); return acc;
}

__device__ __forceinline__ uint32_t lds16x2(uint32_t a) {
  uint16_t v; asm volatile("ld.shared.u16 %0, [%1];" : "=h"(v) : "r"(a) : "memory"); return (uint32_t)v * 0x10001u;
}
__device__ __forceinline__ uint32_t lds32(uint32_t a) {
  uint32_t v; asm volatile("ld.shared.u32 %0, [%1];" : "=r"(v) : "r"(a) : "memory"); return v;
}
__device__ __forceinline__ float2 lds64(uint32_t a) {
  float2 v; asm volatile("ld.shared.v2.f32 {%0, %1}, [%2];" : "=f"(v.x), "=f"(v.y) : "r"(a) : "memory"); return v;
}
__device__ __forceinline__ float4 lds128(uint32_t a) {
  float4 v; asm volatile("ld.shared.v4.f32 {%0, %1, %2, %3}, [%4];" : "=f"(v.x), "=f"(v.y), "=f"(v.z), "=f"(v.w) : "r"(a) : "memory"); return v;
}
__device__ __forceinline__ uint4 lds128u(uint32_t a) {
  uint4 v; asm volatile("ld.shared.v4.u32 {%0, %1, %2, %3}, [%4];" : "=r"(v.x), "=r"(v.y), "=r"(v.z), "=r"(v.w) : "r"(a) : "memory"); return v;
}
__device__ __forceinline__ void sts32(uint32_t a, uint32_t x) { asm volatile("st.shared.u32 [%0], %1;" ::"r"(a), "r"(x) : "memory"); }
__device__ __forceinline__ void sts64(uint32_t a, float x, float y) {
  asm volatile("st.shared.v2.f32 [%0], {%1, %2};" ::"r"(a), "f"(x), "f"(y) : "memory");
}
__device__ __forceinline__ void sts64u(uint32_t a, uint32_t x, uint32_t y) {
  asm volatile("st.shared.v2.u32 [%0], {%1, %2};" ::"r"(a), "r"(x), "r"(y) : "memory");
}
__device__ __forceinline__ void sts128(uint32_t a, float x, float y, float z, float w) {
  asm volatile("st.shared.v4.f32 [%0], {%1, %2, %3, %4};" ::"r"(a), "f"(x), "f"(y), "f"(z), "f"(w) : "memory");
}
__device__ __forceinline__ void sts128u(uint32_t a, uint4 v) {
  asm volatile("st.shared.v4.u32 [%0], {%1, %2, %3, %4};" ::"r"(a), "r"(v.x), "r"(v.y), "r"(v.z), "r"(v.w) : "memory");
}

__device__ __forceinline__ uint32_t pack_bf16(float lo, float hi) {
  uint32_t r; asm("cvt.rn.bf16x2.f32 %0, %1, %2;" : "=r"(r) : "f"(hi), "f"(lo)); return r;
}
__device__ __forceinline__ uint32_t mul_bf16x2(uint32_t a, uint32_t b) {
  uint32_t r; asm("mul.rn.bf16x2 %0, %1, %2;" : "=r"(r) : "r"(a), "r"(b)); return r;
}
__device__ __forceinline__ uint32_t add_bf16x2(uint32_t a, uint32_t b) {
  uint32_t r; asm("add.rn.bf16x2 %0, %1, %2;" : "=r"(r) : "r"(a), "r"(b)); return r;
}
__device__ __forceinline__ uint32_t fma_bf16x2(uint32_t a, uint32_t b, uint32_t c) {
  uint32_t r; asm("fma.rn.bf16x2 %0, %1, %2, %3;" : "=r"(r) : "r"(a), "r"(b), "r"(c)); return r;
}
__device__ __forceinline__ float bf_lo(uint32_t v) { return __uint_as_float(v << 16); }
__device__ __forceinline__ float bf_hi(uint32_t v) { return __uint_as_float(v & 0xffff0000u); }
__device__ __forceinline__ float bf_round(float x) { return __bfloat162float(__float2bfloat16_rn(x)); }
__device__ __forceinline__ float dot8(const uint4& a, const uint4& b) {
  const uint32_t p0 = mul_bf16x2(a.x, b.x), p1 = mul_bf16x2(a.y, b.y), p2 = mul_bf16x2(a.z, b.z), p3 = mul_bf16x2(a.w, b.w);
  return ((bf_lo(p0) + bf_hi(p0)) + (bf_lo(p1) + bf_hi(p1))) + ((bf_lo(p2) + bf_hi(p2)) + (bf_lo(p3) + bf_hi(p3)));
}

constexpr float GELU_A = 0.330078125f;
constexpr uint32_t GELU_A2 = 0x3ea93ea9u, GELU_K2 = 0x401b401bu;
__device__ __forceinline__ uint32_t gelu_pair(float a0, float a1, uint32_t b) {
  const uint32_t z = fma_bf16x2(pack_bf16(a0, a1), GELU_A2, b);
  uint32_t t;
  asm("tanh.approx.bf16x2 %0, %1;" : "=r"(t) : "r"(mul_bf16x2(z, fma_bf16x2(z, z, GELU_K2))));
  return fma_bf16x2(z, t, z);
}
__device__ __forceinline__ void gelu_unit(const float* a, uint32_t* h, uint32_t b0, uint32_t b1) {
#pragma unroll
  for (int i = 0; i < 4; i++) h[i] = gelu_pair(a[2 * i], a[2 * i + 1], (i & 2) ? b1 : b0);
#pragma unroll
  for (int i = 0; i < 4; i++) asm volatile("" : "+r"(h[i])::"memory");
}
__device__ __forceinline__ void cstep(float& hr, float& hi, float lr, float li, float ur, float ui) {
  float nr = fmaf(-li, hi, fmaf(lr, hr, ur));
  float ni = fmaf(li, hr, fmaf(lr, hi, ui));
  hr = nr; hi = ni;
}
__device__ __forceinline__ void cmul(float& ar, float& ai, float br, float bi) {
  float nr = fmaf(ar, br, -ai * bi);
  float ni = fmaf(ar, bi, ai * br);
  ar = nr; ai = ni;
}

__device__ __forceinline__ void part_load(const char* p, uint32_t (&v)[16]) {
#pragma unroll
  for (int i = 0; i < 4; i++) ld_pkt(p + i * 4096, v + 4 * i);
}
__device__ __forceinline__ void part_add(uint32_t (&t)[16], const uint32_t (&v)[16]) {
#pragma unroll
  for (int i = 0; i < 16; i++) { t[i] = add_bf16x2(t[i], v[i]); asm volatile("" : "+r"(t[i])::"memory"); }
}
__device__ __forceinline__ void part_fma(uint32_t (&t)[16], const uint32_t (&v)[16], uint32_t c0, uint32_t c1) {
#pragma unroll
  for (int i = 0; i < 16; i++) { t[i] = fma_bf16x2(v[i], (i & 1) ? c1 : c0, t[i]); asm volatile("" : "+r"(t[i])::"memory"); }
}
__device__ __forceinline__ void part_lds(uint32_t (&o)[16], uint32_t a, uint32_t stride) {
#pragma unroll
  for (int k = 0; k < 4; k++) {
    const uint4 t = lds128u(a + k * stride);
    o[4 * k] = t.x; o[4 * k + 1] = t.y; o[4 * k + 2] = t.z; o[4 * k + 3] = t.w;
  }
}
__device__ __forceinline__ void part_pack(const float (&d)[32], uint32_t (&o)[16]) {
#pragma unroll
  for (int i = 0; i < 16; i++) o[i] = pack_bf16(d[2 * i], d[2 * i + 1]);
}

template <int K> __device__ __forceinline__ void keep_alive(const uint32_t (&o)[16], uint32_t v) {
  asm volatile("{\n.reg .pred p;\nsetp.eq.u32 p, %0, %17;\n"
               "@p st.shared.v4.u32 [%0], {%1, %2, %3, %4};\n@p st.shared.v4.u32 [%0 + 16], {%5, %6, %7, %8};\n"
               "@p st.shared.v4.u32 [%0 + 32], {%9, %10, %11, %12};\n@p st.shared.v4.u32 [%0 + 48], {%13, %14, %15, %16};\n}\n"
               ::"r"(v), "r"(o[0]), "r"(o[1]), "r"(o[2]), "r"(o[3]), "r"(o[4]), "r"(o[5]), "r"(o[6]), "r"(o[7]), "r"(o[8]), "r"(o[9]),
               "r"(o[10]), "r"(o[11]), "r"(o[12]), "r"(o[13]), "r"(o[14]), "r"(o[15]), "n"(2 * K + 1) : "memory");
}

__device__ __forceinline__ void ffn_step(float (&d)[48], uint32_t xo, int j) {
#pragma unroll
  for (int k = 0; k < 4; k++)
    wgmma_ss_n96<0, 1>(d, desc(xo, OFF_X + (j & 7) * SLOT + k * 32, 16, 1024, 1),
                       desc(0, OFF_R + ((8 + j) % NRING) * SLOT + k * 1024, 4096, 512, 2), (j & 7) | k);
}
__device__ __forceinline__ void ffn_step(float (&d)[64], uint32_t xo, int j) {
#pragma unroll
  for (int k = 0; k < 4; k++)
    wgmma_ss_n128<0, 1>(d, desc(xo, OFF_X + (j & 7) * SLOT + k * 32, 16, 1024, 1),
                        desc(0, OFF_R + ((8 + j) % NRING) * SLOT + k * 2048, 8192, 1024, 1), (j & 7) | k);
}

template <int V> struct IC { static constexpr int value = V; };
template <int B, int E, class F>
__device__ __forceinline__ void static_for(F&& f) {
  if constexpr (B < E) { f(IC<B>{}); static_for<B + 1, E>(f); }
}
__host__ __device__ constexpr int gslot(int p, int part) {
  constexpr int tab[8][3] = {{2, 12, 8}, {3, 4, 5}, {9, 10, 11}, {7, 2, 12}, {3, 4, 8}, {5, 9, 10}, {11, 2, 12}, {7, 3, 4}};
  return tab[p][part];
}
__host__ __device__ constexpr int done(int t, int j) {
  constexpr int tab[4][16] = {{T_P1}, {T_CF}, {T_P2}, {T_G1}};
  int n = 0;
  for (int i = 0; i < j; i++) n += tab[t][i];
  return n;
}
static_assert(done(0, 16) == 31 && done(1, 16) == 32 && done(2, 16) == 16 && done(3, 16) == U1, "schedule");

constexpr int XP_END = (done(2, 15) == 16) ? 15 : 16;

__global__ void __cluster_dims__(2, 1, 1) __launch_bounds__(NTHREADS, 1)
fused_kernel(const __nv_bfloat16* __restrict__ p_lre, const __nv_bfloat16* __restrict__ p_lim, const __nv_bfloat16* __restrict__ p_ldt,
             const __nv_bfloat16* __restrict__ p_gw, Scratch* __restrict__ scr, const float sgn, const __grid_constant__ Params P) {
  extern __shared__ __align__(1024) uint8_t smem_raw[];
  const int tid = threadIdx.x;
  const int lane = tid & 31;
  const int warp = __reduce_or_sync(0xffffffffu, (unsigned)tid >> 5);
  const int rank = blockIdx.x & 1, cl = blockIdx.x >> 1;
  const int sl = (cl & 2) | ((cl >> 5) << 2) | rank, tile = (cl & 1) | ((cl >> 1) & 14);
  const uint32_t cb = (uint32_t)rank << 24;

  auto kperm = [&](int s) { return ((s >> 1) == 3) ? (sl & 6) + (s & 1) : ((s >> 1) == (sl >> 1) ? 6 + (s & 1) : s); };
  auto load_x = [&](int s) { tma5<true>(cb + OFF_X + kperm(s) * SLOT + rank * 8192, &P.mx, cb + bar(B_FULL + s), s * 64, rank * 8, tile); };
  auto load_w = [&](int f) {
    if (f >= 2 && f < 8) load_x(f);
    const uint32_t dst = cb + OFF_R + (f % NRING) * SLOT;
    if (f < 8) tma4(dst, &P.mb, cb + bar(B_FULL + f), f * 64, sl * 8);
    else if (f < 16) tma3(dst, &P.mw1b, cb + bar(B_FULL + f), kperm(f & 7) * 64, 32 + sl * 3);
    else tma3(dst, &P.mw1a, cb + bar(B_FULL + f), kperm(f & 7) * 64, sl * 2);
  };
  if (warp == 8) {
    if (elect_one()) {
      mbar_init(cb + bar(B_FULL), 1); mbar_init(cb + bar(B_FULL + 1), 1);
      mbar_expect(cb + bar(B_FULL), 32768); mbar_expect(cb + bar(B_FULL + 1), 32768);
      asm volatile("fence.mbarrier_init.release.cluster;" ::: "memory");
    }
    __syncwarp();
    cluster_arrive();
    if (elect_one()) {
      tma5<false>(cb + OFF_X + kperm(0) * SLOT, &P.mx, cb + bar(B_FULL), 0, 0, tile);
      tma5<false>(cb + OFF_X + kperm(0) * SLOT + 8192, &P.mx, cb + bar(B_FULL), 0, 8, tile);
      load_w(0);
      load_w(1);
    }
    __syncwarp();
    cluster_wait();
    if (elect_one()) load_x(1);
    __syncwarp();
  } else {
    if (warp == 11 && elect_one()) { prefetch_map(&P.mx); prefetch_map(&P.mb); }
    if (warp != 11 && elect_one()) {
      if (warp < 8) {
        const uint32_t b0 = cb + bar(8 * warp), cnt = (warp < 4) ? 1 : 8;
        if (warp > 0) { mbar_init(b0, cnt); mbar_init(b0 + 8, cnt); }
#pragma unroll
        for (int i = 2; i < 8; i++) mbar_init(b0 + 8 * i, cnt);
        if (warp < 4) {
          const uint32_t bytes = (warp == 0) ? 32768 : (warp == 1) ? U1 * 2048 : (warp == 2) ? U2 * 2048 : 45056;
          if (warp > 0) { mbar_expect(b0, (warp == 3) ? U1 * 2048 : bytes); mbar_expect(b0 + 8, (warp == 3) ? U1 * 2048 : bytes); }
#pragma unroll
          for (int i = 2; i < 8; i++) mbar_expect(b0 + 8 * i, bytes);
        }
      } else if (warp == 9) {
        mbar_init(cb + bar(B_FULL0S), 1); mbar_init(cb + bar(B_FULL1S), 1); mbar_init(cb + bar(B_FULL01B), 1); mbar_init(cb + bar(B_G), 1);
        mbar_expect(cb + bar(B_FULL0S), 16384); mbar_expect(cb + bar(B_FULL1S), 16384); mbar_expect(cb + bar(B_FULL01B), U2 * 4096);
        mbar_init(cb + bar(B_PAR), 3); mbar_init(cb + bar(B_S), 2); mbar_init(cb + bar(B_F), 8); mbar_init(cb + bar(B_H), 8);
      } else {
#pragma unroll
        for (int i = 0; i < 8; i++) mbar_init(cb + bar(B_D + i), 1);
#pragma unroll
        for (int i = 0; i < 8; i++) mbar_expect(cb + bar(B_D + i), 8192);
      }
      asm volatile("fence.mbarrier_init.release.cluster;" ::: "memory");
    }
    __syncwarp();
    cluster_arrive();
  }

  if (warp < 8) {
    asm volatile("setmaxnreg.inc.sync.aligned.u32 224;");
    const int wg = warp >> 2;
    const int r = lane >> 2, q = lane & 3;
    const uint32_t xo = wg * 512;
    const uint32_t rbase = __shfl_sync(0xffffffffu, (lane == 0) ? cb : 0x80000000u, lane);

    float sv[64];
#pragma unroll
    for (int i = 0; i < 64; i++) sv[i] = 0.f;
    reg_fence(sv);
    cluster_wait();
    {
      uint32_t ro = (NRING - 1) * SLOT / 16;
      uint32_t eb = bar(B_EMPTY) - 16;
#pragma unroll 1
      for (int k = -1; k < 8; k++) {
        if (k >= 0) mbar_wait(cb + bar(B_FULL) + 8 * k);
        wg_fence();
#pragma unroll
        for (int j = 0; j < 4; j++)
          wgmma_ss_n128<0, 0>(sv, desc(ro + xo, OFF_R + j * 32, 16, 1024, 1),
                              desc(kperm(k & 7) * (SLOT / 16), OFF_X + j * 32, 16, 1024, 1), j == 0 ? k : 1);
        wg_commit();
        wg_wait<1>();
        if (k > 0) lane_arrive(rbase, eb);
        ro += SLOT / 16; if (ro == NRING * SLOT / 16) ro = 0;
        eb += 8;
      }
    }

    float acc1[8 * U1], acc2[8 * U2];
    uint32_t h1[4 * U1], h2[4 * U2], hs[32];
    float4 par;
    float sr, si;
    uint4 gq, bq;
    const uint32_t bias_q = cb + OFF_B1 + q * 16;
    const uint32_t faddr = cb + OFF_F + q * F_STRIDE + (8 * warp + r) * 8;
    const int trail = wg ^ 1;
    uint32_t xo2;
    static_for<0, 16>([&](auto J) {
      constexpr int j = decltype(J)::value;
      constexpr int a0 = done(0, j), a1 = done(0, j + 1), f0 = done(1, j), f1 = done(1, j + 1);
      constexpr int u0 = done(2, j), u1 = done(2, j + 1), g0 = done(3, j), g1 = done(3, j + 1);
      mbar_wait(cb + bar(B_FULL + 8 + j));
      if (j == XP_END) warp_arrive(cb + bar(B_H));
      wg_fence();
      if constexpr (j < 8) ffn_step(acc1, xo, j); else ffn_step(acc2, xo2, j);
      wg_commit();
      if (j >= 8 && !(u0 == 0 && u1 > 0)) sched_fence<24 + j>(rbase);
      if (j == 7) xo2 = __reduce_or_sync(0xffffffffu, xo);
      if (j == 0) {
        mbar_wait(cb + bar(B_PAR));
        par = lds128(cb + OFF_PAR + (8 * warp + r) * 16);
      }
      if (u0 == 0 && u1 > 0) {
        mbar_wait(cb + bar(B_G));
        mbar_wait(cb + bar(B_S));
        const float2 a = lds64(faddr);
        sr = a.x; si = a.y;
      }
      if (j == 7) bq = lds128u(bias_q + 256);
      constexpr bool early = (j == 0 && a1 > 0) || (j == 8 && g1 > 0);
      auto release = [&]() {
        wg_wait<1>();
        lane_arrive(rbase, bar(B_EMPTY + 7 + j));
        if (j == 0) reg_fence(sv);
        if (j == 8) reg_fence(acc1);
      };
      if (early) release();
      if constexpr (a1 > a0) {
        if (a0 == 0) { sr = sv[0]; si = sv[2]; }
#pragma unroll
        for (int i = a0 + 1; i <= a1; i++) cstep(sr, si, par.x, par.y, sv[4 * (i >> 1) + (i & 1)], sv[4 * (i >> 1) + (i & 1) + 2]);
        if (a1 == 31) { sts64(faddr, sr, si); warp_arrive(cb + bar(B_F)); }
        else asm volatile("" : "+f"(sr), "+f"(si)::"memory");
      }
#pragma unroll
      for (int i = f0; i < f1; i++) {
        const int e = 4 * (i >> 1) + (i & 1);
        asm volatile("" : "+f"(sv[e]), "+f"(sv[e + 2])::"memory");
        cmul(sv[e], sv[e + 2], par.z, par.w);
        asm volatile("" : "+f"(sv[e]), "+f"(sv[e + 2])::"memory");
      }
#pragma unroll
      for (int jj = u0; jj < u1; jj++) {
        if ((jj & 3) == 0) gq = lds128u(cb + OFF_RHO + q * 64 + jj * 4);
        const uint32_t g2 = (jj & 2) ? ((jj & 1) ? gq.w : gq.z) : ((jj & 1) ? gq.y : gq.x);
        cstep(sr, si, par.x, par.y, sv[4 * jj], sv[4 * jj + 2]);
        const float tr = sr, ti = si;
        cstep(sr, si, par.x, par.y, sv[4 * jj + 1], sv[4 * jj + 3]);
        hs[2 * jj] = mul_bf16x2(pack_bf16(tr, sr), g2);
        hs[2 * jj + 1] = mul_bf16x2(pack_bf16(ti, si), g2);
        asm volatile("" : "+r"(hs[2 * jj]), "+r"(hs[2 * jj + 1])::"memory");
      }
#pragma unroll
      for (int g = g0; g < g1; g++) {
        gelu_unit(acc1 + 8 * g, h1 + 4 * g, (g & 1) ? bq.z : bq.x, (g & 1) ? bq.w : bq.y);
        if (g & 1) bq = lds128u(bias_q + (g + 1 < U1 ? 256 + (g + 1) * 32 : 0));
      }
      if (j == XP_ST) mbar_wait(cb + bar(B_EMPTY + 17));
      if constexpr (j >= XP_ST && j < XP_END) {
        constexpr int s0 = (j == XP_ST) ? 0 : (u0 / 2 < 2 * (j - XP_ST) ? u0 / 2 : 2 * (j - XP_ST));
        constexpr int s1 = (j == XP_END - 1) ? 8 : (u1 / 2 < 2 * (j + 1 - XP_ST) ? u1 / 2 : 2 * (j + 1 - XP_ST));
        const uint32_t sa = cb + OFF_X + ((lane >> 4) * 16 + ((lane >> 3) & 1) * 8 + warp) * 128 + (lane & 7) * 16;
#pragma unroll
        for (int u = s0; u < s1; u++)
          asm volatile("stmatrix.sync.aligned.m8n8.x4.shared.b16 [%0], {%1, %2, %3, %4};"
                       ::"r"(sa + u * 4096), "r"(hs[4 * u]), "r"(hs[4 * u + 1]), "r"(hs[4 * u + 2]), "r"(hs[4 * u + 3]) : "memory");
      }
      if (!early) release();
      if (XP_END == 16 && j == 15) warp_arrive(cb + bar(B_H));
    });

    float acc[32], acc0[32];
    auto issue_1 = [&](float (&d)[32], int p) {
#pragma unroll
      for (int k = 0; k < U1; k++)
        wgmma_rs_n64<0, 1>(d, h1 + 4 * k, desc(gslot(p, 0) == 7 ? -rank * (SLOT / 16) : 0, OFF_X + gslot(p, 0) * SLOT + k * 2048, 8192, 1024, 1), k);
    };
    auto issue_s = [&](float (&d)[32], int p) {
#pragma unroll
      for (int k = 0; k < 4; k++) wgmma_rs_n64<0, 0, 1>(d, hs + 4 * k, desc(0, OFF_X + gslot(p, 1) * SLOT + k * 32, 16, 1024, 1), 1);
#pragma unroll
      for (int k = 0; k < 4; k++)
        wgmma_rs_n64<0, 0, -1>(d, hs + 16 + 4 * k, desc(0, OFF_X + gslot(p, 1) * SLOT + 8192 + k * 32, 16, 1024, 1), 1);
    };
    auto issue_2 = [&](float (&d)[32], int p) {
#pragma unroll
      for (int k = 0; k < U2; k++) wgmma_rs_n64<0, 1>(d, h2 + 4 * k, desc(0, OFF_X + gslot(p, 2) * SLOT + k * 2048, 8192, 1024, 1), 1);
    };
    auto load_hs = [&]() {
      mbar_wait(cb + bar(B_H));
      const uint32_t la = cb + OFF_X + ((2 * warp + ((lane >> 3) & 1)) * 16 + (lane >> 4)) * 128 + (lane & 7) * 16;
#pragma unroll
      for (int k = 0; k < 8; k++)
        asm volatile("ldmatrix.sync.aligned.m8n8.x4.trans.shared.b16 {%0, %1, %2, %3}, [%4];"
                     : "=r"(hs[4 * k]), "=r"(hs[4 * k + 1]), "=r"(hs[4 * k + 2]), "=r"(hs[4 * k + 3]) : "r"(la + k * 256) : "memory");
    };
    if (trail == 1) {
      mbar_wait(cb + bar(B_FULLG));
      wg_fence();
      issue_1(acc0, 0);
      load_hs();
      mbar_wait(cb + bar(B_FULLG + 1));
      wg_fence();
      issue_1(acc, 1);
      mbar_wait(cb + bar(B_FULL0S));
      wg_fence();
      issue_s(acc0, 0);
      wg_commit();
      wg_wait<1>();
      lane_arrive(rbase, bar(B_EMPTY + 23));
      lane_arrive_remote(rbase ^ (1u << 24), bar(B_PEER));
      mbar_wait(cb + bar(B_FULL1S));
      wg_fence();
      issue_s(acc, 1);
      wg_commit();
      nbar_sync(2, 256);
      wg_wait<1>();
      lane_arrive(rbase, bar(B_AS0));
    } else {
      load_hs();
      wg_wait<0>();
    }
    reg_fence(acc2);
    const uint32_t ltag = lds32(cb + OFF_TAG);
#pragma unroll
    for (int u = 0; u < U2; u++) {
      if (u > 0 && !(u & 1)) bq = lds128u(bias_q + u * 32);
      gelu_unit(acc2 + 8 * u, h2 + 4 * u, (u & 1) ? bq.z : bq.x, (u & 1) ? bq.w : bq.y);
      if (u == 2) {
        const uint32_t b = (trail ? 0x80000000u : rbase) | (ltag >> 1);
        lane_arrive(b, bar(B_EMPTY + 23));
        lane_arrive_remote(b ^ (1u << 24), bar(B_PEER));
      }
    }
    mbar_wait(cb + bar(B_FULL01B));
    nbar_sync(2 + trail, 256);
    if (!trail) { wg_fence(); issue_1(acc0, 0); issue_s(acc0, 0); }
    wg_fence();
    issue_2(acc0, 0);
    wg_commit();
    if (!trail) {
      wg_fence();
      issue_1(acc, 1);
      wg_commit();
      wg_wait<1>();
      lane_arrive(rbase, bar(B_AS0));
      wg_fence();
      issue_s(acc, 1);
    }
    wg_fence();
    issue_2(acc, 1);
    wg_commit();
    nbar_arrive(2 + (trail ^ 1), 256);

    uint32_t v[16] = {}, v2[16], tot[16], pk[16], c0, c1;
    char* const pb = (char*)scr->part + (size_t)tile * (8 * 2 * 16384) + tid * 16;
    auto send_ptr = [&](int rd) { return pb + (uint32_t)((rd < 3) ? sl * 2 + rd - 1 : ((sl - 2) & 7) * 2) * 16384u; };
    auto recv_ptr = [&](int rd) { return pb + (uint32_t)((rd < 3) ? ((sl - 2 * rd) & 7) * 2 + rd - 1 : sl * 2) * 16384u; };
    auto round_tag = [&](int rd) { return (rd == 1) ? 1u : (rd == 2) ? ltag : 0u; };
    const uint32_t dloc = cb + OFF_X + tid * 16;
    auto send_peer = [&](const uint32_t (&o)[16], int i) {
      const uint32_t a = (dloc ^ (1u << 24)) + (i & 1) * SLOT, b = (cb ^ (1u << 24)) + bar(B_D + 2 * i) + 8 * wg;
#pragma unroll
      for (int k = 0; k < 4; k++) st_peer(a + k * 4096, b, o[4 * k], o[4 * k + 1], o[4 * k + 2], o[4 * k + 3]);
    };
    auto recv_peer = [&](uint32_t (&o)[16], int i) {
      mbar_wait(cb + bar(B_D + 2 * i) + 8 * wg);
      part_lds(o, dloc + (i & 1) * SLOT, 4096);
    };
    auto send_far = [&](uint32_t (&o)[16], int rd) {
      char* sp = send_ptr(rd);
      const uint32_t tg = round_tag(rd);
#pragma unroll
      for (int k = 0; k < 4; k++) {
        o[4 * k] = (o[4 * k] & ~1u) | tg;
        st_pkt(sp + k * 4096, o[4 * k], o[4 * k + 1], o[4 * k + 2], o[4 * k + 3]);
      }
    };
    auto collect = [&](int rd) {
      const uint32_t tg = round_tag(rd);
      int it = 0;
      while (__any_sync(0xffffffffu, or_xor(or_xor(or_xor(v[0] ^ tg, v[4], tg), v[8], tg), v[12], tg) & 1u) && ++it < POLL_LIMIT)
        part_load(recv_ptr(rd), v);
      if (rd == 2) { v[0] ^= tg; v[4] ^= tg; v[8] ^= tg; v[12] ^= tg; }
    };
    mbar_wait(cb + bar(B_PEER));
    wg_wait<1>();
    reg_fence(acc0);
    part_pack(acc0, pk);
    send_peer(pk, 0);
    static_for<1, 7>([&](auto PP) {
      constexpr int p = decltype(PP)::value;
      if (p > 1) mbar_wait(cb + bar(B_FULLG + p + 1)); else sched_fence<p>(rbase);
      wg_wait<0>();
      reg_fence(acc);
      if (p < 5) lane_arrive(rbase, bar(B_EMPTYG + p));
      if (p == 6) part_load(recv_ptr(3), v);
      if (p == 1) {
        part_pack(acc, v);
#pragma unroll
        for (int i = 0; i < 16; i++) asm volatile("" : "+r"(v[i])::"memory");
      } else {
        part_pack(acc, pk);
        if (p & 1) { part_add(pk, v2); send_far(pk, (p + 1) / 2); }
        else send_peer(pk, p / 2);
      }
      if (p == 1) mbar_wait(cb + bar(B_FULLG + 2));
      nbar_sync(2 + trail, 256);
      wg_fence();
      issue_1(acc, p + 1); issue_s(acc, p + 1); issue_2(acc, p + 1);
      wg_commit();
      if (!trail || p < 6) nbar_arrive(2 + (trail ^ 1), 256);
      if (p > 1) keep_alive<48 + p>(pk, rbase);
      sched_fence<8 + p>(rbase);
      if (p == 1) { recv_peer(v2, 0); part_add(v, v2); send_far(v, 1); }
      if (!(p & 1)) recv_peer(v2, p / 2);
      if (p >= 4) collect(p - 3);
      if (p == 4 || p == 5) part_fma(tot, v, c0, c1);
      if (p == 3) {
        mbar_wait(cb + bar(B_INI));
        const int trow = 32 * (r >> 1) + 4 * warp + (r & 1);
        c0 = lds16x2(cb + OFF_PHI + trow * 2); c1 = lds16x2(cb + OFF_PHI + trow * 2 + 4);
        part_lds(tot, cb + OFF_X + (6 + rank) * SLOT + warp * 2048 + lane * 16, 512);
      }
      if (p == 3 || p == 4) part_load(recv_ptr(p - 2), v);
    });

    const uint32_t ob = cb + OFF_X + 9 * SLOT + warp * 4096;
    uint32_t oa = ob + r * 128 + (q & 1) * 8 + (((q >> 1) ^ r) << 4);
    asm volatile("" : "+r"(oa)::"memory");
    float pre[16];
    auto half_pre = [&](int hh) {
#pragma unroll
      for (int i = 0; i < 8; i++) {
        const uint32_t c = (i & 1) ? c1 : c0;
        const uint32_t t = fma_bf16x2(v2[8 * hh + i], c, fma_bf16x2(v[8 * hh + i], c, tot[8 * hh + i]));
        pre[2 * i] = bf_lo(t) * (1.f / GELU_A); pre[2 * i + 1] = bf_hi(t) * (1.f / GELU_A);
      }
    };
    half_pre(0);
    reg_fence(pre);
    sched_fence<7>(rbase);
    wg_wait<0>();
    reg_fence(acc);
    const float f0 = bf_hi(c0) * (1.f / GELU_A), f1 = bf_hi(c1) * (1.f / GELU_A);
    const bool lead = elect_one();
    static_for<0, 2>([&](auto H) {
      constexpr int hh = decltype(H)::value;
      if (hh == 1) half_pre(1);
#pragma unroll
      for (int i = 0; i < 4; i++) {
        const uint32_t o = (oa ^ (i << 5)) + hh * 2048;
        const float* a = acc + 16 * hh + 4 * i;
        sts64(o, fmaf(a[0], f0, pre[4 * i]), fmaf(a[1], f0, pre[4 * i + 1]));
        sts64(o + 1024, fmaf(a[2], f1, pre[4 * i + 2]), fmaf(a[3], f1, pre[4 * i + 3]));
      }
      asm volatile("fence.proxy.async.shared::cta;" ::: "memory");
      __syncwarp();
      if (lead) tma5_store(&P.mo, ob + hh * 2048, sl * 64 + 32 * hh, 2 * warp, tile);
      if (hh == 0) sched_fence<18>(rbase);
    });
    if (lead) {
      asm volatile("cp.async.bulk.commit_group;" ::: "memory");
      asm volatile("cp.async.bulk.wait_group.read 0;" ::: "memory");
    }
  } else {
    asm volatile("setmaxnreg.dec.sync.aligned.u32 56;");
    auto skip_terms = [&]() {
      mbar_wait(cb + bar(B_G));
      mbar_wait(cb + bar(B_EMPTYG + 1));
      const int r = lane >> 2, q = lane & 3;
      uint4 ds[2], b2[2];
#pragma unroll
      for (int hh = 0; hh < 2; hh++) { ds[hh] = lds128u(cb + OFF_DS + q * 32 + hh * 16); b2[hh] = lds128u(cb + OFF_B2 + q * 32 + hh * 16); }
#pragma unroll 1
      for (int wv = warp - 9; wv < 8; wv += 3) {
        const int trow = 32 * (r >> 1) + 4 * wv + (r & 1);
        const uint32_t g0 = lds16x2(cb + OFF_G + trow * 2), g1 = lds16x2(cb + OFF_G + trow * 2 + 4);
        const uint32_t o0 = lds16x2(cb + OFF_OMG + trow * 2), o1 = lds16x2(cb + OFF_OMG + trow * 2 + 4);
        const uint32_t base = cb + OFF_X + (6 + rank) * SLOT + wv * 2048;
        const uint32_t xa = base + (lane & 15) * 128 + (((lane >> 4) ^ (lane & 7)) << 4);
        uint4 x[4];
#pragma unroll
        for (int k = 0; k < 4; k++)
          asm volatile("ldmatrix.sync.aligned.m8n8.x4.shared.b16 {%0, %1, %2, %3}, [%4];"
                       : "=r"(x[k].x), "=r"(x[k].y), "=r"(x[k].z), "=r"(x[k].w) : "r"(xa ^ (k << 5)) : "memory");
#pragma unroll
        for (int k = 0; k < 4; k++) {
          const uint32_t da = (k & 1) ? ds[k >> 1].z : ds[k >> 1].x, db = (k & 1) ? ds[k >> 1].w : ds[k >> 1].y;
          const uint32_t ba = (k & 1) ? b2[k >> 1].z : b2[k >> 1].x, bb = (k & 1) ? b2[k >> 1].w : b2[k >> 1].y;
          x[k].x = mul_bf16x2(fma_bf16x2(mul_bf16x2(x[k].x, da), g0, mul_bf16x2(ba, o0)), GELU_A2);
          x[k].y = mul_bf16x2(fma_bf16x2(mul_bf16x2(x[k].y, da), g1, mul_bf16x2(ba, o1)), GELU_A2);
          x[k].z = mul_bf16x2(fma_bf16x2(mul_bf16x2(x[k].z, db), g0, mul_bf16x2(bb, o0)), GELU_A2);
          x[k].w = mul_bf16x2(fma_bf16x2(mul_bf16x2(x[k].w, db), g1, mul_bf16x2(bb, o1)), GELU_A2);
        }
        __syncwarp();
#pragma unroll
        for (int k = 0; k < 4; k++) sts128u(base + k * 512 + lane * 16, x[k]);
        warp_arrive(cb + bar(B_INI));
      }
    };
    if (warp == 9 || warp == 10) {
      const int h = tid - 288;
      const int ch = sl * 64 + h;
      uint2* const my_pkt = scr->carry + tile * 512 + ch;
      uint32_t* const my_g = scr->gate + tile * 128 + sl * 16 + (h >> 2);
      const uint32_t tag = ld_tag(my_pkt), gtag = ld_tag(my_g);
      const uint4 wv = __ldg((const uint4*)p_gw + h);
      {
        const float Lr = __bfloat162float(p_lre[ch]), Li = __bfloat162float(p_lim[ch]);
        const float dt = bf_round(expf(__bfloat162float(p_ldt[ch])));
        float e = expf(dt * Lr), sn, cs;
        sincospif(dt * Li * 0.31830988618379067f, &sn, &cs);
        const float lr = e * cs, li = e * sn;
        const float sc = __fdividef(1.f, fmaxf(fabsf(Lr), fabsf(Li)));
        const float xr = Lr * sc, xi = Li * sc;
        const float den = __fdividef(2.f * sc, xr * xr + xi * xi);
        const float nr = lr - 1.f;
        sts128(cb + OFF_PAR + h * 16, lr, li * sgn, (nr * xr + li * xi) * den * sgn, (li * xr - nr * xi) * den);
        float ar = lr, ai = li * sgn;
#pragma unroll
        for (int i = 0; i < 5; i++) cmul(ar, ai, ar, ai);
        float br = ar, bi = ai;
#pragma unroll
        for (int i = 0; i < 2; i++) cmul(br, bi, br, bi);
        sts128(cb + OFF_PW + h * 16, ar, ai, br, bi);
      }
      sts128u(cb + OFF_GW + h * 16, wv);
      cluster_wait();
      if (h == 0) sts32(cb + OFF_TAG, tag);
      warp_arrive(cb + bar(B_PAR));
      {
        const int i = h >> 2, n = 64 * (sl & 1) + 8 * (i >> 1) + 2 * (sl >> 1) + (i & 1);
        const int c = (h & 3) | ((i & 1) << 2);
        const uint32_t xa0 = cb + OFF_X + n * 128 + ((c ^ (n & 7)) << 4);
        mbar_wait(cb + bar(B_PAR));
        float s = 0.f;
#pragma unroll 1
        for (int k = 0; k < 8; k += 2) {
          const uint32_t xa = xa0 + kperm(k) * SLOT, wa = cb + OFF_GW + k * 128 + (c << 4), wb = wa + 128;
          mbar_wait(cb + bar(B_FULL) + 8 * k);
          mbar_wait(cb + bar(B_FULL) + 8 * k + 8);
          const uint4 w0 = lds128u(wa), w1 = lds128u(wa ^ 64), w2 = lds128u(wb), w3 = lds128u(wb ^ 64);
          const uint4 x0 = lds128u(xa), x1 = lds128u(xa ^ 64), x2 = lds128u(xa + SLOT), x3 = lds128u((xa ^ 64) + SLOT);
          s += (dot8(x0, w0) + dot8(x1, w1)) + (dot8(x2, w2) + dot8(x3, w3));
        }
        s += __shfl_xor_sync(0xffffffffu, s, 2);
        s += __shfl_xor_sync(0xffffffffu, s, 1);
        const float gv = bf_round(__fdividef(1.f, 1.f + __expf(-bf_round(s))));
        if ((lane & 3) == 0) asm volatile("st.relaxed.gpu.global.u32 [%0], %1;" ::"l"(my_g), "r"(__float_as_uint(gv) | gtag) : "memory");
        nbar_arrive(1, 96);
      }
      const float4 par = lds128(cb + OFF_PAR + h * 16);
      const float4 pw = lds128(cb + OFF_PW + h * 16);
      const float lr = pw.x, li = pw.y, Lr = pw.z, Li = pw.w;
      uint64_t v[15];
#pragma unroll
      for (int i = 0; i < 15; i++) { v[i] = tag; asm volatile("" : "+l"(v[i])::"memory"); }
      mbar_wait(cb + bar(B_F));
      float2 f[4];
#pragma unroll
      for (int s = 0; s < 4; s++) f[s] = lds64(cb + OFF_F + s * F_STRIDE + h * 8);
#pragma unroll
      for (int s = 1; s < 4; s++) {
        float er = f[s - 1].x, ei = f[s - 1].y;
        cstep(er, ei, lr, li, f[s].x, f[s].y);
        f[s].x = er; f[s].y = ei;
      }
      st_pkt8(my_pkt, (__float_as_uint(f[3].x) & ~1u) | tag, __float_as_uint(f[3].y));
      sched_fence<0>(cb);
#pragma unroll
      for (int s = 0; s < 3; s++) cmul(f[s].x, f[s].y, par.z, par.w);
      mbar_wait(cb + bar(B_EMPTY + 11));
#pragma unroll 1
      for (int it = 0; it < POLL_LIMIT; it++) {
        const int tl = tile | (it >> 28);
        static_for<0, 15>([&](auto I) {
          constexpr int i = decltype(I)::value;
          asm volatile("{\n.reg .pred p;\nsetp.ge.s32 p, %2, %3;\n@p ld.relaxed.gpu.global.b64 %0, [%1 + %4];\n}\n"
                       : "+l"(v[i]) : "l"(my_pkt), "r"(tl), "n"(15 - i), "n"((i - 15) * 4096) : "memory");
        });
        uint32_t bad = 0;
#pragma unroll
        for (int i = 0; i < 15; i++) bad = or_xor(bad, (uint32_t)v[i], tag);
        if (!__any_sync(0xffffffffu, bad & 1u)) break;
      }
      float zr = __uint_as_float((uint32_t)v[0] ^ tag), zi = __uint_as_float((uint32_t)(v[0] >> 32));
#pragma unroll
      for (int i = 1; i < 15; i++) cstep(zr, zi, Lr, Li, __uint_as_float((uint32_t)v[i] ^ tag), __uint_as_float((uint32_t)(v[i] >> 32)));
      cmul(zr, zi, par.z, par.w);
      sts64(cb + OFF_F + h * 8, zr, zi);
#pragma unroll
      for (int s = 1; s < 4; s++) {
        cmul(zr, zi, lr, li);
        sts64(cb + OFF_F + s * F_STRIDE + h * 8, zr + f[s - 1].x, zi + f[s - 1].y);
      }
      warp_arrive(cb + bar(B_S));
      skip_terms();
    } else if (warp == 11) {
      trap_if_ne(cb + SBASE, (uint32_t)__cvta_generic_to_shared(smem_raw));
      if (elect_one()) {
        prefetch_map(&P.mw1b); prefetch_map(&P.mw1a); prefetch_map(&P.mw2b); prefetch_map(&P.mc[0]); prefetch_map(&P.mc[1]);
        prefetch_map(&P.mw2a); prefetch_map(&P.mo);
      }
      const int q = lane & 3, i = lane >> 2;
      uint32_t b1v[4];
#pragma unroll
      for (int k = 0; k < 4; k++) {
        const int e = 32 * k + lane;
        b1v[k] = __ldg((const uint32_t*)P.b1 + ((k < 2) ? sl * 64 + e : 512 + sl * 48 + min(e - 64, 47)));
      }
      const uint32_t dsv = __ldg((const uint32_t*)(P.dskip + sl * 64) + lane), b2v = __ldg((const uint32_t*)(P.b2 + sl * 64) + lane);
      const size_t b = blockIdx.x;
      cluster_wait();
      mbar_wait(cb + bar(B_FULL + 3));
      if (elect_one()) {
#pragma unroll
        for (int k = 0; k < 4; k++) prefetch_l2((const char*)P.w1 + b * 14336 + k * 3584 + 2048, 1536);
      }
#pragma unroll
      for (int k = 0; k < 4; k++) sts32(cb + OFF_B1 + (2 * k + (i >> 2)) * 64 + q * 16 + (i & 3) * 4, mul_bf16x2(b1v[k], GELU_A2));
      sts32(cb + OFF_DS + q * 32 + i * 4, dsv);
      sts32(cb + OFF_B2 + q * 32 + i * 4, b2v);
      warp_arrive(cb + bar(B_PAR));
      mbar_wait(cb + bar(B_FULL + 7));
      if (elect_one()) {
#pragma unroll
        for (int k = 0; k < 4; k++) prefetch_l2((const char*)P.w1 + b * 14336 + k * 3584, 2048);
      }
      mbar_wait(cb + bar(B_FULL + 9));
      if (elect_one()) {
        prefetch_l2((const char*)P.w2 + b * 14336, 14336);
        prefetch_l2((const char*)P.cre + b * 4096, 4096);
        prefetch_l2((const char*)P.cim + b * 4096, 4096);
      }
      nbar_sync(1, 96);
      const uint32_t tag = lds32(cb + OFF_TAG);
      uint32_t v[4];
      for (int it = 0; it < POLL_LIMIT; it++) {
        ld_pkt(scr->gate + tile * 128 + lane * 4, v);
        if (!__any_sync(0xffffffffu, ((v[0] ^ tag) | (v[1] ^ tag) | (v[2] ^ tag) | (v[3] ^ tag)) & 1u)) break;
      }
      uint32_t g2[2], o2[2], p2[2], r2[2];
#pragma unroll
      for (int k = 0; k < 2; k++) {
        g2[k] = __byte_perm(v[2 * k], v[2 * k + 1], 0x7632);
        o2[k] = add_bf16x2(0x3f803f80u, g2[k] ^ 0x80008000u);
        p2[k] = pack_bf16(fmaxf(0.5f * bf_lo(o2[k]), 1e-12f), fmaxf(0.5f * bf_hi(o2[k]), 1e-12f));
        r2[k] = pack_bf16(__fdividef(GELU_A * bf_lo(g2[k]), bf_lo(p2[k])), __fdividef(GELU_A * bf_hi(g2[k]), bf_hi(p2[k])));
      }
      sts64u(cb + OFF_G + lane * 8, g2[0], g2[1]);
      sts64u(cb + OFF_OMG + lane * 8, o2[0], o2[1]);
      sts64u(cb + OFF_PHI + lane * 8, p2[0], p2[1]);
      sts64u(cb + OFF_RHO + lane * 8, r2[0], r2[1]);
      warp_arrive(cb + bar(B_G));
      skip_terms();
    } else {
      if (elect_one()) {
#pragma unroll
        for (int f = 2; f < 24; f++) {
          if (f >= NRING) mbar_wait(cb + bar(B_EMPTY + f - NRING));
          load_w(f);
        }
        auto load_g = [&](int p, int part, int b) {
          const int d = (((sl + 2 + (p & 6)) & 7) ^ (~p & 1)) * 64;
          const uint32_t dst = cb + OFF_X + (gslot(p, part) - (gslot(p, part) == 7 ? rank : 0)) * SLOT;
          if (part == 0) tma2(dst, &P.mw2b, cb + bar(b), d, 1024 + sl * 96);
          else if (part == 2) tma2(dst, &P.mw2a, cb + bar(b), d, sl * 128);
          else { tma2(dst, &P.mc[0], cb + bar(b), sl * 64, d); tma2(dst + 8192, &P.mc[1], cb + bar(b), sl * 64, d); }
        };
        load_g(0, 0, B_FULLG);
        mbar_wait(cb + bar(B_EMPTY + 19));
        load_g(1, 0, B_FULLG + 1);
        load_g(0, 1, B_FULL0S);
        mbar_wait(cb + bar(B_EMPTY + 20));
        load_g(1, 1, B_FULL1S);
        load_g(0, 2, B_FULL01B);
        mbar_wait(cb + bar(B_EMPTY + 21));
        load_g(1, 2, B_FULL01B);
        mbar_wait(cb + bar(B_EMPTY + 22));
        load_g(2, 0, B_FULLG + 2);
        load_g(2, 1, B_FULLG + 2);
        mbar_wait(cb + bar(B_EMPTY + 23));
        load_g(2, 2, B_FULLG + 2);
        load_g(3, 0, B_FULLG + 3);
        mbar_wait(cb + bar(B_AS0));
        load_g(3, 1, B_FULLG + 3);
        load_g(3, 2, B_FULLG + 3);
        static_for<4, 8>([&](auto PP) {
          constexpr int p = decltype(PP)::value;
          mbar_wait(cb + bar(B_EMPTYG + p - 3));
          if (p == 4) load_g(p, 0, B_FULLG + p);
          load_g(p, 1, B_FULLG + p);
          load_g(p, 2, B_FULLG + p);
          if constexpr (p < 7) load_g(p + 1, 0, B_FULLG + p + 1);
        });
      }
    }
  }
}

typedef CUresult (*EncodeFn)(CUtensorMap*, CUtensorMapDataType, cuuint32_t, void*, const cuuint64_t*, const cuuint64_t*,
                             const cuuint32_t*, const cuuint32_t*, CUtensorMapInterleave, CUtensorMapSwizzle,
                             CUtensorMapL2promotion, CUtensorMapFloatOOBfill);

void encode(EncodeFn fn, CUtensorMap* m, const void* ptr, int rank, const cuuint64_t* dim, const cuuint64_t* str,
            const cuuint32_t* box, CUtensorMapSwizzle sw, CUtensorMapDataType dt = CU_TENSOR_MAP_DATA_TYPE_BFLOAT16) {
  cuuint32_t es[5] = {1, 1, 1, 1, 1};
  fn(m, dt, rank, const_cast<void*>(ptr), dim, str, box, es, CU_TENSOR_MAP_INTERLEAVE_NONE, sw,
     CU_TENSOR_MAP_L2_PROMOTION_L2_128B, CU_TENSOR_MAP_FLOAT_OOB_FILL_NONE);
}

}

extern "C" void kernel_launch(void* const* d_in, const int* in_sizes, int n_in, void* d_out, int out_size) {
  (void)in_sizes; (void)n_in; (void)out_size;
  static EncodeFn fn = nullptr;
  static Scratch* scr = nullptr;
  if (!fn) {
    void* p = nullptr;
    cudaDriverEntryPointQueryResult st;
    cudaGetDriverEntryPoint("cuTensorMapEncodeTiled", &p, cudaEnableDefault, &st);
    fn = (EncodeFn)p;
    cudaGetSymbolAddress((void**)&scr, g_scratch);
    cudaFuncSetAttribute(fused_kernel, cudaFuncAttributeMaxDynamicSharedMemorySize, SMEM_BYTES);
  }
  typedef const __nv_bfloat16* bp;
  Params P;
  P.cre = (bp)d_in[5]; P.cim = (bp)d_in[6]; P.dskip = (bp)d_in[8];
  P.w1 = (bp)d_in[10]; P.b1 = (bp)d_in[11]; P.w2 = (bp)d_in[12]; P.b2 = (bp)d_in[13];
  {
    cuuint64_t dim[5] = {512, 2, 4, 16, 16}, str[4] = {1024, 32768, 2048, 131072};
    cuuint32_t box[5] = {64, 2, 4, 8, 1};
    encode(fn, &P.mx, d_in[0], 5, dim, str, box, CU_TENSOR_MAP_SWIZZLE_128B);
  }
  const bool swapped = (uintptr_t)d_in[4] < (uintptr_t)d_in[3];
  {
    const uintptr_t lo = (uintptr_t)d_in[swapped ? 4 : 3], hi = (uintptr_t)d_in[swapped ? 3 : 4];
    cuuint64_t dim[4] = {512, 8, 2, 64}, str[3] = {1024, hi - lo, 8192};
    cuuint32_t box[4] = {64, 8, 2, 8};
    encode(fn, &P.mb, (const void*)lo, 4, dim, str, box, CU_TENSOR_MAP_SWIZZLE_128B);
  }
  {
    cuuint64_t dim[2] = {512, 512}, str[1] = {1024};
    cuuint32_t box[2] = {64, 64};
    encode(fn, &P.mc[0], swapped ? P.cim : P.cre, 2, dim, str, box, CU_TENSOR_MAP_SWIZZLE_128B);
    encode(fn, &P.mc[1], swapped ? P.cre : P.cim, 2, dim, str, box, CU_TENSOR_MAP_SWIZZLE_128B);
  }
  {
    cuuint64_t dima[3] = {64, 512, 28}, stra[2] = {3584, 128}, dimb[3] = {32, 512, 56}, strb[2] = {3584, 64};
    cuuint32_t boxa[3] = {64, 64, 2}, boxb[3] = {32, 64, 3};
    encode(fn, &P.mw1a, P.w1, 3, dima, stra, boxa, CU_TENSOR_MAP_SWIZZLE_128B);
    encode(fn, &P.mw1b, P.w1, 3, dimb, strb, boxb, CU_TENSOR_MAP_SWIZZLE_64B);
  }
  {
    cuuint64_t dim[2] = {512, 1792}, str[1] = {1024};
    cuuint32_t boxa[2] = {64, 128}, boxb[2] = {64, 96};
    encode(fn, &P.mw2a, P.w2, 2, dim, str, boxa, CU_TENSOR_MAP_SWIZZLE_128B);
    encode(fn, &P.mw2b, P.w2, 2, dim, str, boxb, CU_TENSOR_MAP_SWIZZLE_128B);
  }
  {
    cuuint64_t dim[5] = {512, 2, 4, 16, 16}, str[4] = {2048, 65536, 4096, 262144};
    cuuint32_t box[5] = {32, 2, 4, 2, 1};
    encode(fn, &P.mo, d_out, 5, dim, str, box, CU_TENSOR_MAP_SWIZZLE_128B, CU_TENSOR_MAP_DATA_TYPE_FLOAT32);
  }
  fused_kernel<<<128, NTHREADS, SMEM_BYTES, cudaStreamPerThread>>>((bp)d_in[1], (bp)d_in[2], (bp)d_in[7], (bp)d_in[14], scr,
                                                                      swapped ? -1.f : 1.f, P);
}
```
